```python
import torch

def _softmax(x, axis=-1):
    return torch.softmax(x, dim=axis)
def _gelu(x):
    return torch.nn.functional.gelu(x, approximate="tanh")
def _silu(x):
    return torch.nn.functional.silu(x)
def _sigmoid(x):
    return torch.sigmoid(x)
def _layernorm(x, axis=-1, eps=1e-5):
    m = x.mean(dim=axis, keepdim=True)
    v = x.var(dim=axis, keepdim=True, unbiased=False)
    return (x - m) / torch.sqrt(v + eps)
def _scatter_add(tgt, idx, src, axis=0):
    return tgt.clone().index_add_(axis, idx, src)
def _segment_sum(src, seg, n):
    out = torch.zeros((n,) + src.shape[1:], dtype=src.dtype)
    return out.index_add_(0, seg, src)
def _pad(x, pw):
    flat = tuple(v for pair in reversed(pw) for v in pair)
    return torch.nn.functional.pad(x, flat)

kernel_name = 'concat_heads__mha_block_cached__gqa_block_cached__near_ridge'

def setup_inputs():

    _w = (lambda a: (lambda t: t.to(torch.bfloat16) if t.is_floating_point() else t)(torch.as_tensor(a)))
    def _A_setup():
        B, Sq, D = 32, 32, 640
        H, Sk, Dh = 32, 32, 128
        return {
            "x": _w((lambda *s: torch.randn(*s, dtype=torch.bfloat16) * 0.8)(B, Sq, D)),
            "k_cache": _w((lambda *s: torch.randn(*s, dtype=torch.bfloat16) * 0.8)(B, H, Sk, Dh)),
            "v_cache": _w((lambda *s: torch.randn(*s, dtype=torch.bfloat16) * 0.05)(B, H, Sk, Dh)),
            "wq": _w((lambda *s: torch.randn(*s, dtype=torch.bfloat16) * 0.8)(D, H * Dh) * (D ** -0.5)),
            "wo": _w((lambda *s: torch.randn(*s, dtype=torch.bfloat16) * 0.05)(H * Dh, D) * ((H * Dh) ** -0.5)),
        }
    _A_in = _A_setup()

    def _B_setup():
        B, Sq, D = 32, 32, 640
        Hq, Hkv, Sk, Dh = 32, 32, 32, 128
        assert Hq % Hkv == 0, (Hq, Hkv)
        return {
            "x": _w((lambda *s: torch.randn(*s, dtype=torch.bfloat16) * 0.8)(B, Sq, D)),
            "k_cache": _w((lambda *s: torch.randn(*s, dtype=torch.bfloat16) * 0.8)(B, Hkv, Sk, Dh)),
            "v_cache": _w((lambda *s: torch.randn(*s, dtype=torch.bfloat16) * 0.05)(B, Hkv, Sk, Dh)),
            "wq": _w((lambda *s: torch.randn(*s, dtype=torch.bfloat16) * 0.8)(D, Hq * Dh) * (D ** -0.5)),
            "wo": _w((lambda *s: torch.randn(*s, dtype=torch.bfloat16) * 0.05)(Hq * Dh, D) * ((Hq * Dh) ** -0.5)),
        }
    _B_in = _B_setup()

    return {
        "A_x": _A_in["x"],
        "A_k_cache": _A_in["k_cache"],
        "A_v_cache": _A_in["v_cache"],
        "A_wq": _A_in["wq"],
        "A_wo": _A_in["wo"],
        "B_x": _B_in["x"],
        "B_k_cache": _B_in["k_cache"],
        "B_v_cache": _B_in["v_cache"],
        "B_wq": _B_in["wq"],
        "B_wo": _B_in["wo"],
    }

def reference(A_x, A_k_cache, A_v_cache, A_wq, A_wo, B_x, B_k_cache, B_v_cache, B_wq, B_wo):
    def _A_ref(x, k_cache, v_cache, wq, wo):
        B, Sq, D = x.shape
        H, Dh = 32, 128
        q = (lambda x, *d: x.permute(*d))((x @ wq).reshape(B, Sq, H, Dh), 0, 2, 1, 3)
        scores = torch.einsum("bhqd,bhkd->bhqk", q, k_cache) * (Dh ** -0.5)
        p = _softmax(scores, axis=-1)
        o = torch.einsum("bhqk,bhkd->bhqd", p, v_cache)
        return (lambda x, *d: x.permute(*d))(o, 0, 2, 1, 3).reshape(B, Sq, H * Dh) @ wo

    def _B_ref(x, k_cache, v_cache, wq, wo):
        B, Sq, D = x.shape
        Hq, Dh = 32, 128
        Hkv = k_cache.shape[1]
        rep = Hq // Hkv
        q = (lambda x, *d: x.permute(*d))((x @ wq).reshape(B, Sq, Hq, Dh), 0, 2, 1, 3)
        k = (lambda x, n, axis: torch.repeat_interleave(x, n, dim=axis))(k_cache, rep, axis=1)
        v = (lambda x, n, axis: torch.repeat_interleave(x, n, dim=axis))(v_cache, rep, axis=1)
        scores = torch.einsum("bhqd,bhkd->bhqk", q, k) * (Dh ** -0.5)
        p = _softmax(scores, axis=-1)
        o = torch.einsum("bhqk,bhkd->bhqd", p, v)
        return (lambda x, *d: x.permute(*d))(o, 0, 2, 1, 3).reshape(B, Sq, Hq * Dh) @ wo

    a = _A_ref(A_x, A_k_cache, A_v_cache, A_wq, A_wo)
    b = _B_ref(B_x, B_k_cache, B_v_cache, B_wq, B_wo)
    return torch.concatenate([a, b], axis=-1)
```

```cpp
#include <cuda_runtime.h>
#include <cuda_bf16.h>
#include <cuda.h>
#include <stdint.h>

namespace {

constexpr int T_INIT = 1700, T_INIT_GAP = 400;
constexpr int T_STREAM = 3900, T_GAP = 595;

constexpr int SLOT = 16384;
constexpr int NSLOT = 14;
constexpr int BAR_OFF = NSLOT * SLOT;
constexpr int SMEM_BYTES = NSLOT * SLOT + 3072;
constexpr int B_WQF = 0;
constexpr int B_XF = 6;
constexpr int B_KVF = 16;
constexpr int B_STE = 26;
constexpr int B_WOF = 30;
constexpr int B_WQE = 42;
constexpr int B_KE = 48;
constexpr int B_WOE = 64;
constexpr int B_STF = 76;
constexpr int B_ZERO = 80;
constexpr int B_DONE = 81;
constexpr int PF_PROG = 768;
constexpr int PF_DUMMY = 800;
constexpr int ZEROS = 1024;

constexpr uint64_t KV_SLOT = 0xBA9D876C5342B1A0ull;
constexpr int kv_slot(int t) { return (int)(KV_SLOT >> (4 * t)) & 15; }
constexpr uint64_t FREED = 0xC90B8A17D65432ull;
constexpr int freed_index(int buf) { int r = 0; for (int i = 0; i < 14; i++) if ((int)((FREED >> (4 * i)) & 15) == buf) r = i; return r; }
constexpr int buf_slot(int buf) { return kv_slot(freed_index(buf)); }
constexpr int wq_pos(int s) { return s < 24 ? (s & 3) + ((s & 3) >> 1) : (s - 24) % 6; }
constexpr int wq_par(int s) { return s < 24 ? (s >> 2) & 1 : ((s - 24) / 6) & 1; }
constexpr int wq_buf(int s) { return (0x1DC0BA >> (4 * wq_pos(s))) & 15; }
constexpr int head_of_step(int t) { return (t & 1) + (t < 2 ? 16 : 0); }
constexpr uint32_t wq_entry(int s) {
    const int pos = wq_pos(s), kb = (s % 20) / 2;
    const int r1 = s < 34 ? B_WQE + pos : B_KE + freed_index(wq_buf(s));
    const int r2 = (s < 20 || !(s & 1)) ? 0 : kb < 2 ? B_WQE + 2 + 3 * kb : B_KE + freed_index(kb);
    return (uint32_t)wq_par(s) << 31 | pos << 28 | buf_slot(wq_buf(s)) << 24 | buf_slot(kb) << 20 | r1 * 8 << 10 | r2 * 8;
}
constexpr uint64_t wq_free_par() {
    uint64_t t = 0;
    for (int s = 0; s < 40; s++) t |= (uint64_t)((wq_par(s) ^ ((wq_pos(s) == 2 || wq_pos(s) == 5) ? 0 : 1)) & 1) << s;
    return t;
}
constexpr uint64_t WQ_FREE_PAR = wq_free_par();
constexpr int SLOT_X0 = buf_slot(0), SLOT_X1 = buf_slot(1), SLOT_X2 = buf_slot(2), SLOT_R0 = buf_slot(10), SLOT_R1 = buf_slot(11), SLOT_R2 = buf_slot(12), SLOT_R3 = buf_slot(13);
constexpr int PF_INIT = 6, PF_UNITS = PF_INIT + 35, PF_TICKS = PF_INIT + 39, PF_WQ_AT = 6, PF_WO_AT = 24;
constexpr uint32_t pf_entry(int i) {
    if (i < PF_INIT) return i == 1 ? (1 << 3 | 4) : i == 3 ? (3 << 3 | 4) : (((i == 0 ? 1 : i == 2 ? 2 : i - 1) * 4096) << 3 | 2);
    const int u = i - PF_INIT;
    if (u >= PF_WQ_AT && u < PF_WQ_AT + 5) return ((u - PF_WQ_AT) * 4096 + 16) << 3 | 2;
    int j = u < PF_WQ_AT ? u : u - 5;
    if (j >= PF_WO_AT) { if (j < PF_WO_AT + 2) return ((j - PF_WO_AT) * 10240) << 3 | 3; j -= 2; }
    const int t = j >> 1, step = t < 8 ? t >> 1 : t & 3, g = t < 8 ? t & 1 : (t >> 2) & 1;
    return (((g * 2 + (j & 1)) * 32 + head_of_step(step)) * 32) << 3 | (t >= 8 ? 1 : 0);
}
constexpr uint32_t kv_entry(int t) {
    const int step = t < 8 ? t >> 1 : t & 3, g = t < 8 ? t & 1 : (t >> 2) & 1;
    const int bar = g * 5 + (t < 8 ? step >> 1 : step < 2 ? 2 : step + 1), n = (t >= 8 && step >= 2) ? 1 : (step & 1) ? 0 : 2;
    int j = 2 * t + 1; if (j >= PF_WO_AT) j += 2; j += PF_INIT + 5;
    j += t < 5 ? 4 : j < PF_UNITS ? 1 : -1;
    return kv_slot(t) | g << 6 | bar << 8 | n << 12 | j << 16 | head_of_step(step) << 24;
}
struct Tables { uint32_t wq[41], pf[PF_TICKS], kv[16]; };
constexpr Tables make_tables() {
    Tables t = {};
    for (int i = 0; i < 40; i++) t.wq[i] = wq_entry(i);
    for (int i = 0; i < PF_UNITS; i++) t.pf[i] = pf_entry(i);
    for (int i = 0; i < 16; i++) t.kv[i] = kv_entry(i);
    return t;
}

constexpr int work_of_cluster(int c) {
    return c < 4 ? 60 + c : c < 36 ? ((c - 2) & 7) * 8 + ((c - 4) >> 3) : (((c - 36) % 7 < 5) ? (c - 36) % 7 + 2 : (c - 36) % 7 - 5) * 8 + 4 + (c - 36) / 7;
}
constexpr uint64_t map_plane(int b) { uint64_t t = 0; for (int c = 0; c < 64; c++) t |= (uint64_t)((work_of_cluster(c) >> b) & 1) << c; return t; }

constexpr uint64_t P0 = map_plane(0), P1 = map_plane(1), P2 = map_plane(2), P3 = map_plane(3), P4 = map_plane(4), P5 = map_plane(5);

struct Branch { CUtensorMap x, wq4, wq, k, v, wo; };
struct Params {
    Branch b[2];
    CUtensorMap out;
    const char* ptr[2][5];
    __nv_bfloat16* outp;
    Tables tab;
};

__device__ unsigned int g_zero_cnt[16];

__device__ __forceinline__ void mbar_init(uint32_t bar, uint32_t cnt) { asm volatile("mbarrier.init.shared::cta.b64 [%0], %1;" :: "r"(bar), "r"(cnt) : "memory"); }
__device__ __forceinline__ void mbar_expect_tx(uint32_t bar, uint32_t bytes) { asm volatile("mbarrier.arrive.expect_tx.shared::cta.b64 _, [%0], %1;" :: "r"(bar), "r"(bytes) : "memory"); }
__device__ __forceinline__ void mbar_arrive_if(uint32_t bar, bool on) {
    asm volatile("{\n.reg .pred p;\nsetp.ne.u32 p, %1, 0;\n@p mbarrier.arrive.shared::cluster.b64 _, [%0];\n}" :: "r"(bar), "r"((uint32_t)on) : "memory");
}
__device__ __forceinline__ void mbar_arrive_if(uint32_t bar, uint32_t cnt, bool on) {
    asm volatile("{\n.reg .pred p;\nsetp.ne.u32 p, %2, 0;\n@p mbarrier.arrive.shared::cluster.b64 _, [%0], %1;\n}" :: "r"(bar), "r"(cnt), "r"((uint32_t)on) : "memory");
}
__device__ __forceinline__ void mbar_wait(uint32_t bar, uint32_t parity) {
    asm volatile("{\n.reg .pred p;\nW:\nmbarrier.try_wait.parity.shared::cta.b64 p, [%0], %1;\n@!p bra.uni W;\n}" :: "r"(bar), "r"(parity) : "memory");
}
__device__ __forceinline__ void mbar_wait_x(uint32_t bar, uint32_t parity) {
    asm volatile("{\n.reg .pred p;\n.reg .u32 n;\nmov.u32 n, 0;\nW:\nmbarrier.try_wait.parity.shared::cta.b64 p, [%0], %1;\n@p bra.uni D;\n"
                 "add.u32 n, n, 1;\nsetp.lt.u32 p, n, 0x40000000;\n@p bra.uni W;\nexit;\nD:\n}" :: "r"(bar), "r"(parity) : "memory");
}
__device__ __forceinline__ void mbar_wait_or_trap(uint32_t bar) {
    asm volatile("{\n.reg .pred p;\n.reg .u32 n;\nmov.u32 n, 0;\nW:\nmbarrier.try_wait.parity.shared::cta.b64 p, [%0], 0, 1000;\n@p bra.uni D;\n"
                 "add.u32 n, n, 1;\nsetp.lt.u32 p, n, 1000000;\n@p bra.uni W;\ntrap;\nD:\n}" :: "r"(bar) : "memory");
}
__device__ __forceinline__ bool elect_one() { uint32_t p; asm volatile("{\n.reg .pred P;\nelect.sync _|P, 0xffffffff;\nselp.u32 %0, 1, 0, P;\n}" : "=r"(p)); return p; }
__device__ __forceinline__ uint32_t clock_lo() { uint64_t t; asm volatile("mov.u64 %0, %%clock64;" : "=l"(t) :: "memory"); return (uint32_t)t; }

__device__ __forceinline__ void tma2d(uint32_t dst, const CUtensorMap* tm, int c0, int c1, uint32_t bar) {
    asm volatile("cp.async.bulk.tensor.2d.shared::cluster.global.mbarrier::complete_tx::bytes [%0], [%1, {%3, %4}], [%2];" :: "r"(dst), "l"(tm), "r"(bar), "r"(c0), "r"(c1) : "memory");
}
__device__ __forceinline__ void tma2d_mc(uint32_t dst, const CUtensorMap* tm, int c0, int c1, uint32_t bar) {
    asm volatile("cp.async.bulk.tensor.2d.shared::cluster.global.mbarrier::complete_tx::bytes.multicast::cluster [%0], [%1, {%3, %4}], [%2], %5;" :: "r"(dst), "l"(tm), "r"(bar), "r"(c0), "r"(c1), "h"((uint16_t)3) : "memory");
}
__device__ __forceinline__ void tma3d(uint32_t dst, const CUtensorMap* tm, int c1, int c2, uint32_t bar) {
    asm volatile("cp.async.bulk.tensor.3d.shared::cluster.global.mbarrier::complete_tx::bytes [%0], [%1, {%3, %4, %5}], [%2];" :: "r"(dst), "l"(tm), "r"(bar), "r"(0), "r"(c1), "r"(c2) : "memory");
}
__device__ __forceinline__ void tma3d_mc(uint32_t dst, const CUtensorMap* tm, int c1, int c2, uint32_t bar) {
    asm volatile("cp.async.bulk.tensor.3d.shared::cluster.global.mbarrier::complete_tx::bytes.multicast::cluster [%0], [%1, {%3, %4, %5}], [%2], %6;" :: "r"(dst), "l"(tm), "r"(bar), "r"(0), "r"(c1), "r"(c2), "h"((uint16_t)3) : "memory");
}
__device__ __forceinline__ void tma4d_stream(uint32_t dst, const CUtensorMap* tm, int c1, int c2, uint32_t bar) {
    asm volatile("{\n.reg .b64 pol;\ncreatepolicy.fractional.L2::evict_first.b64 pol, 1.0;\n"
                 "cp.async.bulk.tensor.4d.shared::cluster.global.mbarrier::complete_tx::bytes.L2::cache_hint [%0], [%1, {%3, %4, %5, %3}], [%2], pol;\n}"
                 :: "r"(dst), "l"(tm), "r"(bar), "r"(0), "r"(c1), "r"(c2) : "memory");
}

__device__ __forceinline__ void wg_fence() { asm volatile("wgmma.fence.sync.aligned;" ::: "memory"); }
__device__ __forceinline__ void wg_commit() { asm volatile("wgmma.commit_group.sync.aligned;" ::: "memory"); }
template <int N> __device__ __forceinline__ void wg_wait() { asm volatile("wgmma.wait_group.sync.aligned %0;" :: "n"(N) : "memory"); }
template <int N> __device__ __forceinline__ void fence_regs(float (&d)[N]) {
#pragma unroll
    for (int i = 0; i < N; i++) asm volatile("" : "+f"(d[i]) :: "memory");
}
template <int N> __device__ __forceinline__ void fence_regs(uint32_t (&d)[N]) {
#pragma unroll
    for (int i = 0; i < N; i++) asm volatile("" : "+r"(d[i]) :: "memory");
}
__device__ __forceinline__ uint32_t pack_bf16(float lo, float hi) { uint32_t r; asm("cvt.rn.bf16x2.f32 %0, %1, %2;" : "=r"(r) : "f"(hi), "f"(lo)); return r; }
__device__ __forceinline__ uint32_t pack_bf16v(float lo, float hi) { uint32_t r; asm volatile("cvt.rn.bf16x2.f32 %0, %1, %2;" : "=r"(r) : "f"(hi), "f"(lo)); return r; }
__device__ __forceinline__ float rcp(float x) { float r; asm("rcp.approx.ftz.f32 %0, %1;" : "=f"(r) : "f"(x)); return r; }
__device__ __forceinline__ float ex2(float x) { float r; asm("ex2.approx.ftz.f32 %0, %1;" : "=f"(r) : "f"(x)); return r; }

__device__ __forceinline__ uint64_t desc(uint32_t lo) { uint64_t d; asm("mov.b64 %0, {%1, 0x40000040};" : "=l"(d) : "r"(lo)); return d; }
template <int TB> __device__ __forceinline__ void wgmma_n256_ss(float (&d)[128], uint64_t descA, uint64_t descB, int scaleD) {
    asm volatile("{\n.reg .pred p;\nsetp.ne.b32 p, %130, 0;\nwgmma.mma_async.sync.aligned.m64n256k16.f32.bf16.bf16 {%0, %1, %2, %3, %4, %5, %6, %7, %8, %9, %10, %11, %12, %13, %14, %15, %16, %17, %18, %19, %20, %21, %22, %23, %24, %25, %26, %27, %28, %29, %30, %31, %32, %33, %34, %35, %36, %37, %38, %39, %40, %41, %42, %43, %44, %45, %46, %47, %48, %49, %50, %51, %52, %53, %54, %55, %56, %57, %58, %59, %60, %61, %62, %63, %64, %65, %66, %67, %68, %69, %70, %71, %72, %73, %74, %75, %76, %77, %78, %79, %80, %81, %82, %83, %84, %85, %86, %87, %88, %89, %90, %91, %92, %93, %94, %95, %96, %97, %98, %99, %100, %101, %102, %103, %104, %105, %106, %107, %108, %109, %110, %111, %112, %113, %114, %115, %116, %117, %118, %119, %120, %121, %122, %123, %124, %125, %126, %127}, %128, %129, p, 1, 1, 0, %131;\n}\n"
        : "+f"(d[0]), "+f"(d[1]), "+f"(d[2]), "+f"(d[3]), "+f"(d[4]), "+f"(d[5]), "+f"(d[6]), "+f"(d[7]), "+f"(d[8]), "+f"(d[9]), "+f"(d[10]), "+f"(d[11]), "+f"(d[12]), "+f"(d[13]), "+f"(d[14]), "+f"(d[15]), "+f"(d[16]), "+f"(d[17]), "+f"(d[18]), "+f"(d[19]), "+f"(d[20]), "+f"(d[21]), "+f"(d[22]), "+f"(d[23]), "+f"(d[24]), "+f"(d[25]), "+f"(d[26]), "+f"(d[27]), "+f"(d[28]), "+f"(d[29]), "+f"(d[30]), "+f"(d[31]), "+f"(d[32]), "+f"(d[33]), "+f"(d[34]), "+f"(d[35]), "+f"(d[36]), "+f"(d[37]), "+f"(d[38]), "+f"(d[39]), "+f"(d[40]), "+f"(d[41]), "+f"(d[42]), "+f"(d[43]), "+f"(d[44]), "+f"(d[45]), "+f"(d[46]), "+f"(d[47]), "+f"(d[48]), "+f"(d[49]), "+f"(d[50]), "+f"(d[51]), "+f"(d[52]), "+f"(d[53]), "+f"(d[54]), "+f"(d[55]), "+f"(d[56]), "+f"(d[57]), "+f"(d[58]), "+f"(d[59]), "+f"(d[60]), "+f"(d[61]), "+f"(d[62]), "+f"(d[63]), "+f"(d[64]), "+f"(d[65]), "+f"(d[66]), "+f"(d[67]), "+f"(d[68]), "+f"(d[69]), "+f"(d[70]), "+f"(d[71]), "+f"(d[72]), "+f"(d[73]), "+f"(d[74]), "+f"(d[75]), "+f"(d[76]), "+f"(d[77]), "+f"(d[78]), "+f"(d[79]), "+f"(d[80]), "+f"(d[81]), "+f"(d[82]), "+f"(d[83]), "+f"(d[84]), "+f"(d[85]), "+f"(d[86]), "+f"(d[87]), "+f"(d[88]), "+f"(d[89]), "+f"(d[90]), "+f"(d[91]), "+f"(d[92]), "+f"(d[93]), "+f"(d[94]), "+f"(d[95]), "+f"(d[96]), "+f"(d[97]), "+f"(d[98]), "+f"(d[99]), "+f"(d[100]), "+f"(d[101]), "+f"(d[102]), "+f"(d[103]), "+f"(d[104]), "+f"(d[105]), "+f"(d[106]), "+f"(d[107]), "+f"(d[108]), "+f"(d[109]), "+f"(d[110]), "+f"(d[111]), "+f"(d[112]), "+f"(d[113]), "+f"(d[114]), "+f"(d[115]), "+f"(d[116]), "+f"(d[117]), "+f"(d[118]), "+f"(d[119]), "+f"(d[120]), "+f"(d[121]), "+f"(d[122]), "+f"(d[123]), "+f"(d[124]), "+f"(d[125]), "+f"(d[126]), "+f"(d[127])
        : "l"(descA), "l"(descB), "r"(scaleD), "n"(TB));
}
template <int TB> __device__ __forceinline__ void wgmma_n64_rs(float (&d)[32], uint32_t a0, uint32_t a1, uint32_t a2, uint32_t a3, uint64_t descB, int scaleD) {
    asm volatile("{\n.reg .pred p;\nsetp.ne.b32 p, %37, 0;\nwgmma.mma_async.sync.aligned.m64n64k16.f32.bf16.bf16 {%0, %1, %2, %3, %4, %5, %6, %7, %8, %9, %10, %11, %12, %13, %14, %15, %16, %17, %18, %19, %20, %21, %22, %23, %24, %25, %26, %27, %28, %29, %30, %31}, {%32, %33, %34, %35}, %36, p, 1, 1, %38;\n}\n"
        : "+f"(d[0]), "+f"(d[1]), "+f"(d[2]), "+f"(d[3]), "+f"(d[4]), "+f"(d[5]), "+f"(d[6]), "+f"(d[7]), "+f"(d[8]), "+f"(d[9]), "+f"(d[10]), "+f"(d[11]), "+f"(d[12]), "+f"(d[13]), "+f"(d[14]), "+f"(d[15]), "+f"(d[16]), "+f"(d[17]), "+f"(d[18]), "+f"(d[19]), "+f"(d[20]), "+f"(d[21]), "+f"(d[22]), "+f"(d[23]), "+f"(d[24]), "+f"(d[25]), "+f"(d[26]), "+f"(d[27]), "+f"(d[28]), "+f"(d[29]), "+f"(d[30]), "+f"(d[31])
        : "r"(a0), "r"(a1), "r"(a2), "r"(a3), "l"(descB), "r"(scaleD), "n"(TB));
}
template <int TB> __device__ __forceinline__ void wgmma_sp_n128_rs(float (&d)[64], uint32_t a0, uint32_t a1, uint32_t a2, uint32_t a3, uint64_t descB, uint32_t meta, int scaleD) {
    asm volatile("{\n.reg .pred p;\nsetp.ne.b32 p, %70, 0;\nwgmma.mma_async.sp.sync.aligned.m64n128k32.f32.bf16.bf16 {%0, %1, %2, %3, %4, %5, %6, %7, %8, %9, %10, %11, %12, %13, %14, %15, %16, %17, %18, %19, %20, %21, %22, %23, %24, %25, %26, %27, %28, %29, %30, %31, %32, %33, %34, %35, %36, %37, %38, %39, %40, %41, %42, %43, %44, %45, %46, %47, %48, %49, %50, %51, %52, %53, %54, %55, %56, %57, %58, %59, %60, %61, %62, %63}, {%64, %65, %66, %67}, %68, %69, 0, p, 1, 1, %71;\n}\n"
        : "+f"(d[0]), "+f"(d[1]), "+f"(d[2]), "+f"(d[3]), "+f"(d[4]), "+f"(d[5]), "+f"(d[6]), "+f"(d[7]), "+f"(d[8]), "+f"(d[9]), "+f"(d[10]), "+f"(d[11]), "+f"(d[12]), "+f"(d[13]), "+f"(d[14]), "+f"(d[15]), "+f"(d[16]), "+f"(d[17]), "+f"(d[18]), "+f"(d[19]), "+f"(d[20]), "+f"(d[21]), "+f"(d[22]), "+f"(d[23]), "+f"(d[24]), "+f"(d[25]), "+f"(d[26]), "+f"(d[27]), "+f"(d[28]), "+f"(d[29]), "+f"(d[30]), "+f"(d[31]), "+f"(d[32]), "+f"(d[33]), "+f"(d[34]), "+f"(d[35]), "+f"(d[36]), "+f"(d[37]), "+f"(d[38]), "+f"(d[39]), "+f"(d[40]), "+f"(d[41]), "+f"(d[42]), "+f"(d[43]), "+f"(d[44]), "+f"(d[45]), "+f"(d[46]), "+f"(d[47]), "+f"(d[48]), "+f"(d[49]), "+f"(d[50]), "+f"(d[51]), "+f"(d[52]), "+f"(d[53]), "+f"(d[54]), "+f"(d[55]), "+f"(d[56]), "+f"(d[57]), "+f"(d[58]), "+f"(d[59]), "+f"(d[60]), "+f"(d[61]), "+f"(d[62]), "+f"(d[63])
        : "r"(a0), "r"(a1), "r"(a2), "r"(a3), "l"(descB), "r"(meta), "r"(scaleD), "n"(TB));
}


__device__ __forceinline__ void issue_pv(float (&o)[64], uint32_t (&pa)[8], uint32_t tile, uint32_t meta) {
    const uint64_t dv = desc(tile + (511 << 16));
    wgmma_sp_n128_rs<1>(o, pa[0], pa[1], pa[2], pa[3], dv, meta, 0);
    wgmma_sp_n128_rs<1>(o, pa[4], pa[5], pa[6], pa[7], dv + (4096 >> 4), meta, 1);
}
__device__ __forceinline__ void pick(float (&v)[16], float (&s)[32], bool hi) {
#pragma unroll
    for (int i = 0; i < 16; i++) v[i] = hi ? s[16 + i] : s[i];
    fence_regs(v);
}
__device__ __forceinline__ void softmax2(float (&a)[16], float (&b)[16], uint32_t (&pa)[8], uint32_t (&pb)[8]) {
    float* v[2] = {a, b};
    float m[4], s[4];
#pragma unroll
    for (int h = 0; h < 2; h++)
#pragma unroll
        for (int r = 0; r < 2; r++) {
            const float* u = v[h] + 2 * r;
            m[2 * h + r] = fmaxf(fmaxf(fmaxf(u[0], u[1]), fmaxf(u[4], u[5])), fmaxf(fmaxf(u[8], u[9]), fmaxf(u[12], u[13])));
        }
#pragma unroll
    for (int i = 0; i < 4; i++) m[i] = fmaxf(m[i], __shfl_xor_sync(0xffffffffu, m[i], 1));
#pragma unroll
    for (int i = 0; i < 4; i++) m[i] = fmaxf(m[i], __shfl_xor_sync(0xffffffffu, m[i], 2));
    const float c = 0.08838834764831845f * 1.4426950408889634f;
#pragma unroll
    for (int h = 0; h < 2; h++)
#pragma unroll
        for (int r = 0; r < 2; r++) {
            float* u = v[h] + 2 * r;
            const float mx = m[2 * h + r];
#pragma unroll
            for (int j = 0; j < 4; j++) { u[4 * j] = ex2((u[4 * j] - mx) * c); u[4 * j + 1] = ex2((u[4 * j + 1] - mx) * c); }
            s[2 * h + r] = ((u[0] + u[1]) + (u[4] + u[5])) + ((u[8] + u[9]) + (u[12] + u[13]));
        }
#pragma unroll
    for (int i = 0; i < 4; i++) s[i] += __shfl_xor_sync(0xffffffffu, s[i], 1);
#pragma unroll
    for (int i = 0; i < 4; i++) s[i] = rcp(s[i] + __shfl_xor_sync(0xffffffffu, s[i], 2));
#pragma unroll
    for (int j = 0; j < 4; j++) {
        pa[2 * j] = pack_bf16(a[4 * j] * s[0], a[4 * j + 1] * s[0]); pa[2 * j + 1] = pack_bf16(a[4 * j + 2] * s[1], a[4 * j + 3] * s[1]);
        pb[2 * j] = pack_bf16(b[4 * j] * s[2], b[4 * j + 1] * s[2]); pb[2 * j + 1] = pack_bf16(b[4 * j + 2] * s[3], b[4 * j + 3] * s[3]);
    }
    fence_regs(pa); fence_regs(pb);
}
__device__ __forceinline__ void to_frags(uint32_t (&q)[32], float (&o)[64]) {
    fence_regs(o);
#pragma unroll
    for (int i = 0; i < 32; i++) q[i] = pack_bf16v(o[2 * i], o[2 * i + 1]);
}

__global__ void __cluster_dims__(2, 1, 1) __launch_bounds__(384, 1) fused_attn_kernel(const __grid_constant__ Params p) {
    extern __shared__ __align__(1024) unsigned char smem_raw[];
    const uint32_t t_entry = clock_lo();
    uint32_t smem = (uint32_t)__cvta_generic_to_shared(smem_raw);
    asm volatile("" : "+r"(smem));
    const uint32_t bars = smem + BAR_OFF;
    const int rank = blockIdx.x & 1;
    auto plane = [&](uint64_t t) { return (int)((uint32_t)(t >> (blockIdx.x >> 1)) & 1); };
    const int br = plane(P5), hg = plane(P4) * 4 + plane(P3) * 2 + plane(P2), mt = plane(P1) * 4 + plane(P0) * 2 + rank;
    const Branch* tm = &p.b[br];
    if (threadIdx.x >= 256 && threadIdx.x < 288) {
        auto ld_x = [&](int kb, int slot) { mbar_expect_tx(bars + (B_XF + kb) * 8, SLOT); tma2d(smem + slot * SLOT, &tm->x, kb * 64, mt * 128, bars + (B_XF + kb) * 8); };
        auto ld_q = [&](int s, int pos, int slot) { mbar_expect_tx(bars + (B_WQF + pos) * 8, SLOT); tma3d(smem + slot * SLOT, &tm->wq4, s * 32, hg * 4, bars + (B_WQF + pos) * 8); };
        if (elect_one()) {
            mbar_init(bars + B_XF * 8, 1); mbar_init(bars + B_WQF * 8, 1); mbar_init(bars + (B_WQF + 1) * 8, 1);
            asm volatile("fence.proxy.async.shared::cta;" ::: "memory");
            ld_q(0, 0, SLOT_R0); ld_x(0, SLOT_X0); ld_q(1, 1, SLOT_R1);
        }
        __syncwarp();
        if (elect_one()) {
#pragma unroll
            for (int i = 2; i <= B_DONE; i++)
                if (i != B_XF) mbar_init(bars + i * 8, i < B_WQE ? 1 : i < B_STF ? 16 : 8);
            asm volatile("fence.mbarrier_init.release.cluster;\nfence.proxy.async.shared::cta;" ::: "memory");
            ld_x(1, SLOT_X1); ld_q(2, 3, SLOT_R2); ld_q(3, 4, SLOT_R3); ld_x(2, SLOT_X2);
        }
        __syncwarp();
    } else if (threadIdx.x < 9) {
        while ((int)(clock_lo() - t_entry) < 450) { }
        asm volatile("st.shared.u32 [%0], %1;" :: "r"(bars + PF_DUMMY), "r"(reinterpret_cast<const uint32_t*>(&p.ptr)[min(threadIdx.x * 16, 123u)]) : "memory");
    }
    const int warp = __shfl_sync(0xffffffffu, (int)(threadIdx.x >> 5), 0);
    const int lane = threadIdx.x & 31;
    if (warp == 10) asm volatile("st.volatile.shared.u32 [%0], %1;\nbar.arrive 0, 384;" :: "r"(bars + PF_PROG), "r"(0) : "memory");
    else asm volatile("bar.sync 0, 384;" ::: "memory");
    asm volatile("barrier.cluster.arrive.relaxed.aligned;" ::: "memory");
    if (warp != 10) asm volatile("barrier.cluster.wait.aligned;" ::: "memory");

    if (warp < 8) {
        asm volatile("setmaxnreg.inc.sync.aligned.u32 240;");
        const int wg = warp >> 2;
        uint32_t bars_sig; asm volatile("mapa.shared::cluster.u32 %0, %1, %2;" : "=r"(bars_sig) : "r"(bars), "r"(lane & 1));
        const bool sig = lane < 2;
        const uint32_t desc0 = ((smem & 0x3FFFF) >> 4) | 1 << 16;
        uint32_t q0[32], q1[32], q2[32], q3[32];

        {
            float acc[128];
            uint32_t rel = 0, e, la, lb, xb, fb;
            auto operands = [&](int s, int i) {
                e = p.tab.wq[s];
                la = desc0 + wg * 512 + ((e >> 10) & 0x3C00) + (i & 1) * 4;
                lb = desc0 + (255 << 16) + ((e >> 14) & 0x3C00);
                xb = bars + (B_XF + (i >> 1)) * 8; fb = bars + B_WQF * 8 + ((e >> 25) & 0x38);
                asm volatile("" : "+r"(e), "+r"(la), "+r"(lb), "+r"(xb), "+r"(fb));
            };
            operands(0, 0);
            int s = 0;
#pragma unroll 1
            for (int pass = 0; pass < 2; pass++) {
#pragma unroll 1
                for (int i = 0; i < 20; i++, s++) {
                    mbar_wait(xb, 0);
                    mbar_wait(fb, e >> 31);
                    asm volatile("{\n.reg .pred p;\nsetp.ne.u32 p, %0, 0;\n@p bar.sync 3, 256;\n}" :: "r"((uint32_t)(i + wg * 64 == 64 + 18)) : "memory");
                    wg_fence();
                    wgmma_n256_ss<1>(acc, desc(la), desc(lb), i != 0);
                    wgmma_n256_ss<1>(acc, desc(la) + 2, desc(lb) + 128, 1);
                    wg_commit();
                    asm volatile("{\n.reg .pred p;\nsetp.ne.u32 p, %0, 0;\n@p bar.arrive 3, 256;\n}" :: "r"((uint32_t)(i + wg * 64 == 19)) : "memory");
                    const uint32_t r1 = (rel >> 10) & 1023, r2 = rel & 1023;
                    rel = e;
                    operands(s + 1, i == 19 ? 0 : i + 1);
                    wg_wait<1>();
                    mbar_arrive_if(bars_sig + r1, sig && r1); mbar_arrive_if(bars_sig + r2, sig && r2);
                }
                wg_wait<0>();
                mbar_arrive_if(bars_sig + ((rel >> 10) & 1023), sig); mbar_arrive_if(bars_sig + (rel & 1023), sig && pass);
                rel = 0;
                fence_regs(acc);
                if (pass == 0) {
#pragma unroll
                    for (int i = 0; i < 32; i++) { q2[i] = pack_bf16v(acc[2 * i], acc[2 * i + 1]); q3[i] = pack_bf16v(acc[64 + 2 * i], acc[64 + 2 * i + 1]); }
                }
            }
#pragma unroll
            for (int i = 0; i < 32; i++) q1[i] = pack_bf16v(acc[64 + 2 * i], acc[64 + 2 * i + 1]);
#pragma unroll
            for (int i = 0; i < 32; i++) q0[i] = pack_bf16v(acc[2 * i], acc[2 * i + 1]);
        }

        const uint32_t stage = smem + (12 + wg) * SLOT + (warp & 3) * 2048;
        const uint32_t st_addr = stage + (lane & 15) * 128 + (((lane >> 4) ^ (lane & 7)) << 4);
        auto put = [&](float (&y)[32], int buf, int j) {
            const uint32_t r0 = pack_bf16v(y[8 * j + 0], y[8 * j + 1]), r1 = pack_bf16v(y[8 * j + 2], y[8 * j + 3]);
            const uint32_t r2 = pack_bf16v(y[8 * j + 4], y[8 * j + 5]), r3 = pack_bf16v(y[8 * j + 6], y[8 * j + 7]);
            asm volatile("stmatrix.sync.aligned.m8n8.x4.shared.b16 [%0], {%1, %2, %3, %4};" :: "r"((st_addr ^ (j * 32)) + buf * 8192), "r"(r0), "r"(r1), "r"(r2), "r"(r3) : "memory");
        };
        float accA[32], accB[32];
        auto tile_mma = [&](float (&x)[32], uint32_t (&o)[32], uint64_t d, bool first, auto&& side) {
            auto mm = [&](int kk) { wgmma_n64_rs<1>(x, o[4 * kk], o[4 * kk + 1], o[4 * kk + 2], o[4 * kk + 3], d + ((kk * 2048) >> 4), !(first && kk == 0)); };
            wg_fence();
            mm(0); mm(1); mm(2); mm(3);
            wg_commit();
            wg_wait<1>();
            side(0); mm(4); side(1); mm(5); side(2); mm(6); side(3); mm(7);
            wg_commit();
        };
        int rb = 4;
        uint32_t par = 0, prev = bars_sig + (B_WOE + 3) * 8;
        auto chunk = [&](float (&x)[32], float (&y)[32], int ch, int buf) {
            const uint64_t d = desc(desc0 + rb * (SLOT >> 4));
            const uint32_t fb = bars + (B_WOF + rb) * 8, eb = bars_sig + (B_WOE + rb) * 8;
            const bool refill = sig && ch < 7;
            mbar_wait(fb, par);
            mbar_wait(bars + (B_STE + 2 * wg + buf) * 8, ((ch + 1) >> 1) & 1);
            tile_mma(x, q0, d, true, [&](int j) { if (j == 0) { mbar_arrive_if(prev, sig && ch < 8); fence_regs(y); } put(y, buf, j); });
            mbar_wait(fb + 8, par);
            tile_mma(x, q1, d + (SLOT >> 4), false, [&](int j) {
                if (j == 0) {
                    mbar_arrive_if(eb, refill);
                    asm volatile("fence.proxy.async.shared::cta;" ::: "memory");
                    __syncwarp();
                    mbar_arrive_if(bars + (B_STF + 2 * wg + buf) * 8, sig);
                }
            });
            mbar_wait(fb + 16, par);
            tile_mma(x, q2, d + 2 * (SLOT >> 4), false, [&](int j) { if (j == 0) mbar_arrive_if(eb + 8, refill); });
            mbar_wait(fb + 24, par);
            tile_mma(x, q3, d + 3 * (SLOT >> 4), false, [&](int j) { if (j == 0) mbar_arrive_if(eb + 16, refill); });
            prev = eb + 24;
            rb += 4; if (rb == 12) { rb = 0; par ^= 1; }
        };

        {
            const bool hi_batch = (warp & 2) != 0;
            const uint32_t k01 = wg * 10, k23 = 2 + wg * 2, v123 = 6 + wg * 3;
            auto slot = [&](int j) { return j < 2 ? k01 + j : j < 4 ? k23 + (j - 2) : j == 4 ? 12 + wg : v123 + (j - 5); };
            auto tile = [&](int j) { return desc0 + slot(j) * (SLOT >> 4); };
            auto done = [&](int j) { mbar_arrive_if(bars_sig + (j < 2 ? (wg ? B_KE + 14 : B_WOE) + j : B_WOE + slot(j)) * 8, lane < 4); };
            auto landed = [&](int i) { mbar_wait_x(bars + (B_KVF + 5 * wg + i) * 8, 0); };
            const uint32_t meta = hi_batch ? 0xDDDDDDDDu : 0x88888888u;
            uint32_t p0[8], p1[8], p2[8], p3[8];
            float va[16], vb[16];
            {
                float sa[32], sb[32];
                auto s_pair = [&](uint32_t (&qa)[32], uint32_t (&qb)[32], int j) {
                    const uint64_t da = desc(tile(j)), db = da + (SLOT >> 4);
                    landed(j >> 1);
                    wg_fence();
#pragma unroll
                    for (int kk = 0; kk < 8; kk++) {
                        const uint32_t o = ((kk >> 2) * 8192 + (kk & 3) * 32) >> 4;
                        wgmma_n64_rs<0>(sa, qa[4 * kk], qa[4 * kk + 1], qa[4 * kk + 2], qa[4 * kk + 3], da + o, kk != 0);
                        wgmma_n64_rs<0>(sb, qb[4 * kk], qb[4 * kk + 1], qb[4 * kk + 2], qb[4 * kk + 3], db + o, kk != 0);
                    }
                    wg_commit();
                };
                s_pair(q0, q1, 0);
                wg_wait<0>(); fence_regs(sa); fence_regs(sb);
                done(0); done(1);
                pick(va, sa, hi_batch); pick(vb, sb, hi_batch);
                s_pair(q2, q3, 2);
                softmax2(va, vb, p0, p1);
                wg_wait<0>(); fence_regs(sa); fence_regs(sb);
                done(2); done(3);
                pick(va, sa, hi_batch); pick(vb, sb, hi_batch);
            }
            float oa[64], ob[64];
            if (wg == 0) {
                landed(2);
                wg_fence(); issue_pv(oa, p0, tile(4), meta); issue_pv(ob, p1, tile(5), meta); wg_commit();
                softmax2(va, vb, p2, p3);
                asm volatile("bar.arrive 4, 256;" ::: "memory");
            } else {
                asm volatile("bar.sync 4, 256;" ::: "memory");
                softmax2(va, vb, p2, p3);
                landed(2);
                wg_fence(); issue_pv(oa, p0, tile(4), meta); issue_pv(ob, p1, tile(5), meta); wg_commit();
            }
            wg_wait<0>();
            done(5);
            const uint64_t d = desc(desc0);
            const uint32_t fb = bars + B_WOF * 8, eb = bars_sig + B_WOE * 8;
            to_frags(q0, oa);
            mbar_wait_x(fb, 0);
            tile_mma(accA, q0, d, true, [&](int j) { if (j == 0) to_frags(q1, ob); });
            landed(3);
            wg_fence(); issue_pv(ob, p2, tile(6), meta); wg_commit();
            mbar_wait_x(fb + 8, 0);
            tile_mma(accA, q1, d + (SLOT >> 4), false, [&](int j) { if (j == 0) { mbar_arrive_if(eb, sig); done(6); to_frags(q2, ob); } });
            landed(4);
            wg_fence(); issue_pv(ob, p3, tile(7), meta); wg_commit();
            mbar_wait_x(fb + 16, 0);
            tile_mma(accA, q2, d + 2 * (SLOT >> 4), false, [&](int j) { if (j == 0) { mbar_arrive_if(eb + 8, sig); done(7); to_frags(q3, ob); } });
            mbar_wait_x(fb + 24, 0);
            tile_mma(accA, q3, d + 3 * (SLOT >> 4), false, [&](int j) { if (j == 0) mbar_arrive_if(eb + 16, sig); });
        }
        asm volatile("bar.sync %0, 128;" :: "r"(wg + 1) : "memory");
#pragma unroll 1
        for (int ch = 1; ; ch += 2) {
            chunk(accB, accA, ch, 0);
            if (ch == 9) break;
            chunk(accA, accB, ch + 1, 1);
        }
        {
            char* op = reinterpret_cast<char*>(p.outp + (size_t)(mt * 128 + warp * 16 + (lane >> 3)) * 1280 + br * 640 + 9 * 64) + (lane & 7) * 16;
            mbar_wait_x(bars + (B_STE + 2 * wg + 1) * 8, 1);
            mbar_arrive_if(bars + B_DONE * 8, lane == 0);
            asm volatile("barrier.cluster.arrive.relaxed.aligned;" ::: "memory");
            wg_wait<0>();
            fence_regs(accB);
#pragma unroll
            for (int j = 0; j < 4; j++) put(accB, 1, j);
            __syncwarp();
#pragma unroll
            for (int i = 0; i < 4; i++) {
                uint32_t v0, v1, v2, v3;
                asm volatile("ld.shared.v4.u32 {%0, %1, %2, %3}, [%4];" : "=r"(v0), "=r"(v1), "=r"(v2), "=r"(v3)
                             : "r"(stage + 8192 + (lane >> 3) * 128 + i * 512 + (((lane & 7) ^ ((i * 4 + (lane >> 3)) & 7)) << 4)) : "memory");
                asm volatile("red.global.add.noftz.v4.bf16x2 [%0], {%1, %2, %3, %4};" :: "l"(op + i * 4 * 2560), "r"(v0), "r"(v1), "r"(v2), "r"(v3) : "memory");
            }
        }
    } else {
        asm volatile("setmaxnreg.dec.sync.aligned.u32 24;");
        if (warp == 11) {
            mbar_wait_or_trap(bars + (B_XF + 9) * 8);
            asm volatile("st.shared.v4.u32 [%0], {%1, %1, %1, %1};\nst.shared.v4.u32 [%0 + 512], {%1, %1, %1, %1};\nst.shared.v2.u32 [%2], {%1, %1};\n"
                         "fence.proxy.async.shared::cta;" :: "r"(bars + ZEROS + lane * 16), "r"(0), "r"(bars + ZEROS + 1024 + lane * 8) : "memory");
            __syncwarp();
            if (elect_one()) {
                char* o = reinterpret_cast<char*>(p.outp + (size_t)(mt * 128 + hg * 16) * 1280 + br * 640);
#pragma unroll 1
                for (int i = 0; i < 16; i++, o += 2560) {
                    asm volatile("cp.async.bulk.global.shared::cta.bulk_group [%0], [%1], 1280;" :: "l"(o), "r"(bars + ZEROS) : "memory");
                    __nanosleep(50);
                }
                asm volatile("cp.async.bulk.commit_group;\ncp.async.bulk.wait_group 0;\nfence.proxy.async.global;" ::: "memory");
                unsigned int* cnt = &g_zero_cnt[br * 8 + mt];
                unsigned int old, cur, n = 0;
                asm volatile("atom.add.release.gpu.global.u32 %0, [%1], 1;" : "=r"(old) : "l"(cnt) : "memory");
#pragma unroll 1
                do {
                    __nanosleep(100);
                    asm volatile("ld.acquire.gpu.global.u32 %0, [%1];" : "=r"(cur) : "l"(cnt) : "memory");
                } while ((int)(cur - ((old & ~7u) + 8u)) < 0 && ++n < (1u << 22));
                asm volatile("fence.proxy.async.global;" ::: "memory");
                mbar_arrive_if(bars + B_ZERO * 8, 8, n < (1u << 22));
            }
            __syncwarp();
            mbar_wait_or_trap(bars + B_DONE * 8);
            asm volatile("barrier.cluster.arrive.relaxed.aligned;\nbarrier.cluster.wait.aligned;" ::: "memory");
        } else if (warp == 8) {
#pragma unroll 1
            for (int s = 4; s < 40; s++) {
                const uint32_t e = p.tab.wq[s];
                const int pass = s >= 20;
                int krow = (s - pass * 20) * 32, cb = hg * 4 + pass * 32 + rank * 2, xcol = ((s + 1) >> 1) * 64;
                uint32_t fb = bars + B_WQF * 8 + ((e >> 25) & 0x38), dst = smem + ((e >> 10) & 0x3C000) + rank * 8192;
                uint32_t xb = bars + B_XF * 8 + xcol / 8, xdst = smem + ((p.tab.wq[s + 1] >> 6) & 0x3C000);
                asm volatile("" : "+r"(krow), "+r"(cb), "+r"(xcol), "+r"(fb), "+r"(dst), "+r"(xb), "+r"(xdst));
                mbar_wait(fb + (B_WQE - B_WQF) * 8, (uint32_t)(WQ_FREE_PAR >> s) & 1);
                if (elect_one()) {
                    mbar_expect_tx(fb, SLOT); tma3d_mc(dst, &tm->wq, krow, cb, fb);
                    if ((s & 1) && s < 18) { mbar_expect_tx(xb, SLOT); tma2d(xdst, &tm->x, xcol, mt * 128, xb); }
                }
            }
            int r = 0; uint32_t par = 0;
#pragma unroll 1
            for (int i = 0; i < 40; i++) {
                uint32_t fb = bars + (B_WOF + r) * 8, dst = smem + r * SLOT + rank * 8192;
                int col = (i >> 2) * 64, row = (hg * 2 + (i & 1) + ((i & 2) ? 0 : 16)) * 128 + rank * 64;
                asm volatile("" : "+r"(fb), "+r"(dst), "+r"(col), "+r"(row));
                mbar_wait(fb + (B_WOE - B_WOF) * 8, par);
                if (elect_one()) { mbar_expect_tx(fb, SLOT); tma2d_mc(dst, &tm->wo, col, row, fb); }
                if (++r == 12) { r = 0; par ^= 1; }
            }
        } else {
            if (warp == 9) {
#pragma unroll 1
                for (int t = 0; t < 16; t++) {
                    const uint32_t e = p.tab.kv[t];
                    const int row = (hg * 2 + (e >> 24)) * 32, batch = mt * 4 + ((e >> 6) & 1) * 2;
                    int c1 = t < 8 ? row : batch, c2 = t < 8 ? batch : row;
                    uint32_t fb = bars + B_KVF * 8 + ((e >> 5) & 0x78), dst = smem + (e & 15) * SLOT;
                    const CUtensorMap* tk = t < 8 ? &tm->k : &tm->v;
                    asm volatile("" : "+r"(c1), "+r"(c2), "+r"(fb), "+r"(dst), "+l"(tk));
                    mbar_wait(bars + (B_KE + t) * 8, 0);
                    while (true) {
                        uint32_t u; asm volatile("ld.volatile.shared.u32 %0, [%1];" : "=r"(u) : "r"(bars + PF_PROG) : "memory");
                        if (u >= ((e >> 16) & 255)) break;
                        __nanosleep(32);
                    }
                    if (elect_one()) { if (e & 0x3000) mbar_expect_tx(fb, (e << 2) & 0xC000); tma4d_stream(dst, tk, c1, c2, fb); }
                }
            } else {
                const uint32_t o_kv = (mt * 128 + hg * 2) * 8192 + lane * 256;
                const uint32_t o_q = (mt * 16 + (lane >> 1)) * 8192 + hg * 512 + (lane & 1) * 256;
                const uint32_t o_o = (hg * 256 + mt * 32 + lane) * 1280;
                const uint32_t o_x = (mt * 128 + hg * 16 + (lane & 15)) * 1280 + (lane >> 4) * 256;
                uint32_t tn = t_entry + T_INIT;
#pragma unroll 1
                for (int u = 0; u < PF_TICKS; u++) {
                    const uint32_t e = p.tab.pf[u], kind = e & 7;
                    const char* a = p.ptr[br][kind] + ((e >> 3) * 256 + (kind < 2 ? o_kv : kind == 2 ? o_q : kind == 3 ? o_o : o_x));
                    asm volatile("" : "+l"(a));
                    asm volatile("cp.async.wait_group 3;" ::: "memory");
                    while ((int)(clock_lo() - tn) < 0) __nanosleep(32);
                    if (u < PF_INIT) asm volatile("prefetch.global.L2 [%0];\nprefetch.global.L2 [%0 + 128];" :: "l"(a) : "memory");
                    else if (u < PF_UNITS) asm volatile("cp.async.ca.shared.global.L2::256B [%0], [%1], 4;" :: "r"(bars + PF_DUMMY + lane * 4), "l"(a) : "memory");
                    asm volatile("cp.async.commit_group;\nst.volatile.shared.u32 [%0], %1;" :: "r"(bars + PF_PROG), "r"(u) : "memory");
                    tn = u == PF_INIT - 1 ? t_entry + T_STREAM + mt * T_GAP / 8 : tn + (u < PF_INIT ? T_INIT_GAP : T_GAP);
                }
                asm volatile("cp.async.wait_all;\nbarrier.cluster.wait.aligned;" ::: "memory");
            }
            const int g = warp - 9;
            mbar_wait(bars + B_ZERO * 8, 0);
#pragma unroll 1
            for (int ch = 0; ch < 9; ch++) {
                const uint32_t b = 2 * g + (ch & 1);
                mbar_wait(bars + (B_STF + b) * 8, (ch >> 1) & 1);
                if (elect_one()) {
                    asm volatile("cp.reduce.async.bulk.tensor.2d.global.shared::cta.add.tile.bulk_group [%0, {%2, %3}], [%1];\n"
                                 "cp.async.bulk.commit_group;\ncp.async.bulk.wait_group.read 0;"
                                 :: "l"(&p.out), "r"(smem + (12 + g) * SLOT + (ch & 1) * 8192), "r"(br * 640 + ch * 64), "r"(mt * 128 + g * 64) : "memory");
                    mbar_arrive_if(bars + (B_STE + b) * 8, true);
                }
                __syncwarp();
            }
        }
    }
}

typedef CUresult (*EncodeFn)(CUtensorMap*, CUtensorMapDataType, cuuint32_t, void*, const cuuint64_t*, const cuuint64_t*, const cuuint32_t*, const cuuint32_t*,
                             CUtensorMapInterleave, CUtensorMapSwizzle, CUtensorMapL2promotion, CUtensorMapFloatOOBfill);

void encode(EncodeFn enc, CUtensorMap* tm, void* ptr, int rank, const cuuint64_t* dims, const cuuint64_t* strides, const cuuint32_t* box, bool p256) {
    const cuuint32_t es[5] = {1, 1, 1, 1, 1};
    enc(tm, CU_TENSOR_MAP_DATA_TYPE_BFLOAT16, rank, ptr, dims, strides, box, es, CU_TENSOR_MAP_INTERLEAVE_NONE, CU_TENSOR_MAP_SWIZZLE_128B,
        p256 ? CU_TENSOR_MAP_L2_PROMOTION_L2_256B : CU_TENSOR_MAP_L2_PROMOTION_L2_128B, CU_TENSOR_MAP_FLOAT_OOB_FILL_NONE);
}

}


extern "C" void kernel_launch(void* const* d_in, const int* in_sizes, int n_in, void* d_out, int out_size) {
    (void)in_sizes; (void)n_in; (void)out_size;
    void* fn = nullptr; cudaDriverEntryPointQueryResult qr;
    cudaGetDriverEntryPoint("cuTensorMapEncodeTiled", &fn, cudaEnableDefault, &qr);
    EncodeFn enc = (EncodeFn)fn;
    Params p;
    for (int b = 0; b < 2; b++) {
        void* x = d_in[b * 5 + 0]; void* k = d_in[b * 5 + 1]; void* v = d_in[b * 5 + 2]; void* wq = d_in[b * 5 + 3]; void* wo = d_in[b * 5 + 4];
        { cuuint64_t d[2] = {640, 1024}, s[1] = {1280}; cuuint32_t bx[2] = {64, 128}; encode(enc, &p.b[b].x, x, 2, d, s, bx, false); }
        { cuuint64_t d[3] = {64, 640, 64}, s[2] = {8192, 128}; cuuint32_t bx[3] = {64, 32, 4}; encode(enc, &p.b[b].wq4, wq, 3, d, s, bx, false); bx[2] = 2; encode(enc, &p.b[b].wq, wq, 3, d, s, bx, false); }
        { cuuint64_t d[4] = {64, 1024, 32, 2}, s[3] = {256, 262144, 128}; cuuint32_t bx[4] = {64, 32, 2, 2}; encode(enc, &p.b[b].k, k, 4, d, s, bx, false); }
        { cuuint64_t d[4] = {64, 32, 1024, 2}, s[3] = {262144, 256, 128}; cuuint32_t bx[4] = {64, 2, 32, 2}; encode(enc, &p.b[b].v, v, 4, d, s, bx, false); }
        { cuuint64_t d[2] = {640, 4096}, s[1] = {1280}; cuuint32_t bx[2] = {64, 64}; encode(enc, &p.b[b].wo, wo, 2, d, s, bx, true); }
        p.ptr[b][0] = (const char*)k; p.ptr[b][1] = (const char*)v; p.ptr[b][2] = (const char*)wq; p.ptr[b][3] = (const char*)wo; p.ptr[b][4] = (const char*)x;
    }
    { cuuint64_t d[2] = {1280, 1024}, s[1] = {2560}; cuuint32_t bx[2] = {64, 64}; encode(enc, &p.out, d_out, 2, d, s, bx, false); }
    p.outp = (__nv_bfloat16*)d_out;
    p.tab = make_tables();
    cudaFuncSetAttribute(fused_attn_kernel, cudaFuncAttributeMaxDynamicSharedMemorySize, SMEM_BYTES);
    fused_attn_kernel<<<128, 384, SMEM_BYTES, cudaStreamPerThread>>>(p);
}
```
